```python
import torch

def _softmax(x, axis=-1):
    return torch.softmax(x, dim=axis)
def _gelu(x):
    return torch.nn.functional.gelu(x, approximate="tanh")
def _silu(x):
    return torch.nn.functional.silu(x)
def _sigmoid(x):
    return torch.sigmoid(x)
def _layernorm(x, axis=-1, eps=1e-5):
    m = x.mean(dim=axis, keepdim=True)
    v = x.var(dim=axis, keepdim=True, unbiased=False)
    return (x - m) / torch.sqrt(v + eps)
def _scatter_add(tgt, idx, src, axis=0):
    return tgt.clone().index_add_(axis, idx, src)
def _segment_sum(src, seg, n):
    out = torch.zeros((n,) + src.shape[1:], dtype=src.dtype)
    return out.index_add_(0, seg, src)
def _pad(x, pw):
    flat = tuple(v for pair in reversed(pw) for v in pair)
    return torch.nn.functional.pad(x, flat)

kernel_name = 'standalone__weight_only_int_gptq__prompt'

def setup_inputs():

    _w = (lambda a: (lambda t: t.to(torch.bfloat16) if t.is_floating_point() else t)(torch.as_tensor(a)))
    B, S, D, F = 1, 2048, 576, 4608
    bits = max(2, min(4, 2))
    pf = 32 // bits
    G = 64 if 64 > 0 else D
    G = max(pf, (G // pf) * pf)
    D = max(G, (D // G) * G)
    ng = D // G
    qmax = 1 << bits
    qw = torch.randint(0, qmax, (D, F)).to(torch.int64)
    packed = torch.zeros((D // pf, F), dtype=torch.int64)
    for i in range(pf):
        packed |= (qw[i::pf] << (i * bits))
    packed = packed.to(torch.int32)
    return {
        "x": _w((lambda *s: torch.randn(*s, dtype=torch.bfloat16) * 0.05)(B, S, D)),
        "qw_packed": _w(packed),
        "scales": _w(torch.abs((lambda *s: torch.randn(*s, dtype=torch.bfloat16) * 0.05)(ng, F)).to(float) * 0.1 + 0.01),
        "zeros": _w(torch.randint(0, qmax, (ng, F)).to(float)),
        "bits": _w((lambda _x: torch.as_tensor(_x, dtype=torch.int32))(bits)),
    }

def reference(x, qw_packed, scales, zeros, bits):
    b = int(bits)
    pf = 32 // b
    mask = (1 << b) - 1
    P, F = qw_packed.shape
    D = P * pf
    ng = scales.shape[0]
    G = D // ng
    shifts = (lambda x, dt: x.to(dt))(torch.arange(pf) * b, qw_packed.dtype)
    qw = ((qw_packed[:, None, :] >> shifts[None, :, None]) & mask).reshape(D, F)
    s = (lambda x, n, axis: torch.repeat_interleave(x, n, dim=axis))(scales, G, axis=0)
    z = (lambda x, n, axis: torch.repeat_interleave(x, n, dim=axis))(zeros, G, axis=0)
    w = ((lambda x, dt: x.to(dt))(qw, x.dtype) - z) * s
    return torch.einsum("bsd,df->bsf", x, w)
```

```cpp
#include <cuda_runtime.h>
#include <cuda_bf16.h>
#include <cuda.h>
#include <stdint.h>

#define PACE 300
#define NEARLY 2
#define DBL 2
#define L2D 1
#define UNR 2
#define STAG 5
#define ABL 0
#define CREG 232

namespace {

constexpr int S_DIM = 2048, K_DIM = 576, F_DIM = 4608;
constexpr int NG = K_DIM / 64;
constexpr int SLAB = 184;
constexpr int NSLAB = 11;
constexpr int NFR = 12;
constexpr int F_CTA = F_DIM / NFR;
constexpr int CHUNK_BYTES = 192 * 128;
constexpr int PIECE_BYTES = 16 * 128;
constexpr int NPIECE = 12;
constexpr int kUnr = UNR;
constexpr int SLOT_BYTES = 1280;
constexpr int OFF_STAGE = NG * CHUNK_BYTES;
constexpr int OFF_RING = OFF_STAGE + 2 * PIECE_BYTES;
constexpr int OFF_BAR = OFF_RING + 4 * SLOT_BYTES;
constexpr int B_SFULL = 0, B_SFREE = 8, B_XDONE = 16, B_WFULL = 24, B_WFREE = 40, B_FIN = 56, B_BLOCK = 104;
constexpr int OFF_TRACE = OFF_BAR + 320;
constexpr int SMEM_BYTES = OFF_TRACE + 768;

#define TR(i)
#define TRL(i)
#define TRG(i)
#define TR_INIT

__device__ __forceinline__ void mbar_wait(uint32_t bar, uint32_t parity) {
    asm volatile(
        "{\n.reg .pred p;\n"
        "LAB_WAIT:\n"
        "mbarrier.try_wait.parity.shared::cta.b64 p, [%0], %1;\n"
        "@p bra LAB_DONE;\n"
        "bra LAB_WAIT;\n"
        "LAB_DONE:\n}\n" ::"r"(bar), "r"(parity) : "memory");
}
__device__ __forceinline__ void mbar_arrive(uint32_t bar) {
    asm volatile("mbarrier.arrive.shared::cta.b64 _, [%0];" ::"r"(bar) : "memory");
}
__device__ __forceinline__ void mbar_arrive_if(uint32_t bar, uint32_t lane) {
    asm volatile("{\n.reg .pred p;\nsetp.eq.u32 p, %1, 0;\n@p mbarrier.arrive.shared::cta.b64 _, [%0];\n}\n" ::"r"(bar), "r"(lane) : "memory");
}

template <int N> struct Wgmma;
template <> struct Wgmma<192> {
    static __device__ __forceinline__ void rs(float (&d)[96], const uint32_t (&a)[4], uint64_t desc, int scale_d) {
        asm volatile(
            "{\n.reg .pred p;\nsetp.ne.b32 p, %101, 0;\n"
            "wgmma.mma_async.sync.aligned.m64n192k16.f32.bf16.bf16 {"
            "%0,%1,%2,%3,%4,%5,%6,%7,%8,%9,%10,%11,%12,%13,%14,%15,%16,%17,%18,%19,%20,%21,%22,%23,"
            "%24,%25,%26,%27,%28,%29,%30,%31,%32,%33,%34,%35,%36,%37,%38,%39,%40,%41,%42,%43,%44,%45,%46,%47,"
            "%48,%49,%50,%51,%52,%53,%54,%55,%56,%57,%58,%59,%60,%61,%62,%63,%64,%65,%66,%67,%68,%69,%70,%71,"
            "%72,%73,%74,%75,%76,%77,%78,%79,%80,%81,%82,%83,%84,%85,%86,%87,%88,%89,%90,%91,%92,%93,%94,%95}, "
            "{%96,%97,%98,%99}, %100, p, 1, 1, 0;\n}\n"
            : "+f"(d[0]), "+f"(d[1]), "+f"(d[2]), "+f"(d[3]), "+f"(d[4]), "+f"(d[5]), "+f"(d[6]), "+f"(d[7]),
              "+f"(d[8]), "+f"(d[9]), "+f"(d[10]), "+f"(d[11]), "+f"(d[12]), "+f"(d[13]), "+f"(d[14]), "+f"(d[15]),
              "+f"(d[16]), "+f"(d[17]), "+f"(d[18]), "+f"(d[19]), "+f"(d[20]), "+f"(d[21]), "+f"(d[22]), "+f"(d[23]),
              "+f"(d[24]), "+f"(d[25]), "+f"(d[26]), "+f"(d[27]), "+f"(d[28]), "+f"(d[29]), "+f"(d[30]), "+f"(d[31]),
              "+f"(d[32]), "+f"(d[33]), "+f"(d[34]), "+f"(d[35]), "+f"(d[36]), "+f"(d[37]), "+f"(d[38]), "+f"(d[39]),
              "+f"(d[40]), "+f"(d[41]), "+f"(d[42]), "+f"(d[43]), "+f"(d[44]), "+f"(d[45]), "+f"(d[46]), "+f"(d[47]),
              "+f"(d[48]), "+f"(d[49]), "+f"(d[50]), "+f"(d[51]), "+f"(d[52]), "+f"(d[53]), "+f"(d[54]), "+f"(d[55]),
              "+f"(d[56]), "+f"(d[57]), "+f"(d[58]), "+f"(d[59]), "+f"(d[60]), "+f"(d[61]), "+f"(d[62]), "+f"(d[63]),
              "+f"(d[64]), "+f"(d[65]), "+f"(d[66]), "+f"(d[67]), "+f"(d[68]), "+f"(d[69]), "+f"(d[70]), "+f"(d[71]),
              "+f"(d[72]), "+f"(d[73]), "+f"(d[74]), "+f"(d[75]), "+f"(d[76]), "+f"(d[77]), "+f"(d[78]), "+f"(d[79]),
              "+f"(d[80]), "+f"(d[81]), "+f"(d[82]), "+f"(d[83]), "+f"(d[84]), "+f"(d[85]), "+f"(d[86]), "+f"(d[87]),
              "+f"(d[88]), "+f"(d[89]), "+f"(d[90]), "+f"(d[91]), "+f"(d[92]), "+f"(d[93]), "+f"(d[94]), "+f"(d[95])
            : "r"(a[0]), "r"(a[1]), "r"(a[2]), "r"(a[3]), "l"(desc), "r"(scale_d));
    }
};
template <> struct Wgmma<184> {
    static __device__ __forceinline__ void rs(float (&d)[96], const uint32_t (&a)[4], uint64_t desc, int scale_d) {
        asm volatile(
            "{\n.reg .pred p;\nsetp.ne.b32 p, %97, 0;\n"
            "wgmma.mma_async.sync.aligned.m64n184k16.f32.bf16.bf16 {"
            "%0,%1,%2,%3,%4,%5,%6,%7,%8,%9,%10,%11,%12,%13,%14,%15,%16,%17,%18,%19,%20,%21,%22,%23,"
            "%24,%25,%26,%27,%28,%29,%30,%31,%32,%33,%34,%35,%36,%37,%38,%39,%40,%41,%42,%43,%44,%45,%46,%47,"
            "%48,%49,%50,%51,%52,%53,%54,%55,%56,%57,%58,%59,%60,%61,%62,%63,%64,%65,%66,%67,%68,%69,%70,%71,"
            "%72,%73,%74,%75,%76,%77,%78,%79,%80,%81,%82,%83,%84,%85,%86,%87,%88,%89,%90,%91}, "
            "{%92,%93,%94,%95}, %96, p, 1, 1, 0;\n}\n"
            : "+f"(d[0]), "+f"(d[1]), "+f"(d[2]), "+f"(d[3]), "+f"(d[4]), "+f"(d[5]), "+f"(d[6]), "+f"(d[7]),
              "+f"(d[8]), "+f"(d[9]), "+f"(d[10]), "+f"(d[11]), "+f"(d[12]), "+f"(d[13]), "+f"(d[14]), "+f"(d[15]),
              "+f"(d[16]), "+f"(d[17]), "+f"(d[18]), "+f"(d[19]), "+f"(d[20]), "+f"(d[21]), "+f"(d[22]), "+f"(d[23]),
              "+f"(d[24]), "+f"(d[25]), "+f"(d[26]), "+f"(d[27]), "+f"(d[28]), "+f"(d[29]), "+f"(d[30]), "+f"(d[31]),
              "+f"(d[32]), "+f"(d[33]), "+f"(d[34]), "+f"(d[35]), "+f"(d[36]), "+f"(d[37]), "+f"(d[38]), "+f"(d[39]),
              "+f"(d[40]), "+f"(d[41]), "+f"(d[42]), "+f"(d[43]), "+f"(d[44]), "+f"(d[45]), "+f"(d[46]), "+f"(d[47]),
              "+f"(d[48]), "+f"(d[49]), "+f"(d[50]), "+f"(d[51]), "+f"(d[52]), "+f"(d[53]), "+f"(d[54]), "+f"(d[55]),
              "+f"(d[56]), "+f"(d[57]), "+f"(d[58]), "+f"(d[59]), "+f"(d[60]), "+f"(d[61]), "+f"(d[62]), "+f"(d[63]),
              "+f"(d[64]), "+f"(d[65]), "+f"(d[66]), "+f"(d[67]), "+f"(d[68]), "+f"(d[69]), "+f"(d[70]), "+f"(d[71]),
              "+f"(d[72]), "+f"(d[73]), "+f"(d[74]), "+f"(d[75]), "+f"(d[76]), "+f"(d[77]), "+f"(d[78]), "+f"(d[79]),
              "+f"(d[80]), "+f"(d[81]), "+f"(d[82]), "+f"(d[83]), "+f"(d[84]), "+f"(d[85]), "+f"(d[86]), "+f"(d[87]),
              "+f"(d[88]), "+f"(d[89]), "+f"(d[90]), "+f"(d[91])
            : "r"(a[0]), "r"(a[1]), "r"(a[2]), "r"(a[3]), "l"(desc), "r"(scale_d));
    }
};

__device__ __forceinline__ void wg_fence() { asm volatile("wgmma.fence.sync.aligned;" ::: "memory"); }
__device__ __forceinline__ void wg_commit() { asm volatile("wgmma.commit_group.sync.aligned;" ::: "memory"); }
template <int N> __device__ __forceinline__ void wg_wait() { asm volatile("wgmma.wait_group.sync.aligned %0;" ::"n"(N) : "memory"); }

__device__ __forceinline__ uint32_t prmt(uint32_t a, uint32_t b, uint32_t c) {
    uint32_t d; asm("prmt.b32 %0, %1, %2, %3;" : "=r"(d) : "r"(a), "r"(b), "r"(c)); return d;
}
__device__ __forceinline__ uint32_t pack_bf2(float lo, float hi) {
    uint32_t d; asm("cvt.rn.bf16x2.f32 %0, %1, %2;" : "=r"(d) : "f"(hi), "f"(lo)); return d;
}
__device__ __forceinline__ uint32_t hi2lo(uint32_t x) {
    uint32_t d;
    asm("{.reg .b16 l, h; .reg .b32 t; mov.b32 {l, h}, %1; mov.b32 t, {h, h}; add.rn.f16x2 %0, t, %2;}" : "=r"(d) : "r"(x), "r"(0x80008000u));
    return d;
}
template <int H> __device__ __forceinline__ uint32_t lut2(uint32_t q, uint32_t z2, uint32_t s2) {
    uint32_t d;
    if (H == 0) asm("{.reg .b16 l, h; .reg .b32 z, s, t; mov.b32 {l, h}, %2; mov.b32 z, {l, l}; mov.b32 {l, h}, %3; mov.b32 s, {l, l}; sub.rn.bf16x2 t, %1, z; mul.rn.bf16x2 %0, t, s;}" : "=r"(d) : "r"(q), "r"(z2), "r"(s2));
    else asm("{.reg .b16 l, h; .reg .b32 z, s, t; mov.b32 {l, h}, %2; mov.b32 z, {h, h}; mov.b32 {l, h}, %3; mov.b32 s, {h, h}; sub.rn.bf16x2 t, %1, z; mul.rn.bf16x2 %0, t, s;}" : "=r"(d) : "r"(q), "r"(z2), "r"(s2));
    return d;
}

template <int V> struct Int { static constexpr int value = V; };
struct Raw { uint32_t w[4][2], s2, z2; };

__device__ __forceinline__ void load_raw(const int* qw, const __nv_bfloat16* sc, const __nv_bfloat16* zr, uint32_t f, int j, Raw& r) {
    const char* pq = (const char*)qw + f * 4u;
#pragma unroll
    for (int kk = 0; kk < 4; kk++)
        asm volatile("ld.global.nc.v2.u32 {%0,%1}, [%2];" : "=r"(r.w[kk][0]), "=r"(r.w[kk][1]) : "l"(pq + (j * 4 + kk) * F_DIM * 4));
    asm volatile("ld.global.nc.u32 %0, [%1];" : "=r"(r.s2) : "l"((const char*)sc + f * 2u + j * F_DIM * 2));
    asm volatile("ld.global.nc.u32 %0, [%1];" : "=r"(r.z2) : "l"((const char*)zr + f * 2u + j * F_DIM * 2));
}
__device__ __forceinline__ void lds_raw(uint32_t aq, uint32_t as, Raw& r) {
#pragma unroll
    for (int kk = 0; kk < 4; kk++)
        asm volatile("ld.shared.v2.u32 {%0,%1}, [%2];" : "=r"(r.w[kk][0]), "=r"(r.w[kk][1]) : "r"(aq + kk * 256) : "memory");
    asm volatile("ld.shared.u32 %0, [%1];" : "=r"(r.s2) : "r"(as) : "memory");
    asm volatile("ld.shared.u32 %0, [%1];" : "=r"(r.z2) : "r"(as + 128) : "memory");
}
__device__ __forceinline__ void dequant(const Raw& r, int sh, uint32_t c22, uint32_t (&a)[4][4]) {
    const uint32_t l[2][2] = {{lut2<0>(0x3F800000u, r.z2, r.s2), lut2<0>(0x40404000u, r.z2, r.s2)},
                              {lut2<1>(0x3F800000u, r.z2, r.s2), lut2<1>(0x40404000u, r.z2, r.s2)}};
#pragma unroll
    for (int kk = 0; kk < 4; kk++)
#pragma unroll
        for (int h = 0; h < 2; h++) {
            const uint32_t u = r.w[kk][h] >> sh;
            const uint32_t sel = ((u & 0x000C000Cu) * 0x40u + (u & 0x00030003u)) * c22 + 0x10101010u;
            a[kk][h] = prmt(l[h][0], l[h][1], sel);
            a[kk][h + 2] = prmt(l[h][0], l[h][1], hi2lo(sel));
        }
}

__device__ __forceinline__ bool elect_one() {
    uint32_t p;
    asm volatile("{\n.reg .pred q;\nelect.sync _|q, 0xffffffff;\nselp.u32 %0, 1, 0, q;\n}" : "=r"(p));
    return p;
}
__device__ __forceinline__ void mbar_init(uint32_t bar, uint32_t cnt) {
    asm volatile("mbarrier.init.shared::cta.b64 [%0], %1;" ::"r"(bar), "r"(cnt) : "memory");
}
__device__ __forceinline__ void tma_load(uint32_t dst, const CUtensorMap* tm, uint32_t bar, int c0, int c1) {
    asm volatile("cp.async.bulk.tensor.2d.shared::cluster.global.mbarrier::complete_tx::bytes [%0], [%1, {%3, %4}], [%2];"
                 ::"r"(dst), "l"(tm), "r"(bar), "r"(c0), "r"(c1) : "memory");
}
__device__ __forceinline__ void tma_store3(const CUtensorMap* tm, uint32_t src, int c0, int c1, int c2) {
    asm volatile("cp.async.bulk.tensor.3d.global.shared::cta.bulk_group [%0, {%2, %3, %4}], [%1];"
                 ::"l"(tm), "r"(src), "r"(c0), "r"(c1), "r"(c2) : "memory");
}

__global__ void __launch_bounds__(384, 1)
gptq_gemm_kernel(const __grid_constant__ CUtensorMap tm_x, const __grid_constant__ CUtensorMap tm_xe,
                 const __grid_constant__ CUtensorMap tm_o, const __grid_constant__ CUtensorMap tm_oe,
                 const __grid_constant__ CUtensorMap tm_q, const __grid_constant__ CUtensorMap tm_s,
                 const __grid_constant__ CUtensorMap tm_z,
                 const int* __restrict__ qw, const __nv_bfloat16* __restrict__ scales,
                 const __nv_bfloat16* __restrict__ zeros) {
    extern __shared__ __align__(1024) uint8_t smem[];
    const uint32_t sbase = (uint32_t)__cvta_generic_to_shared(smem);
    const int warp = __shfl_sync(0xffffffffu, threadIdx.x >> 5, 0);
    const int slab = blockIdx.y, f_cta = blockIdx.x * F_CTA;
    const int rot = slab % 3;
    const bool has_extra = slab < 9;
    const int s_extra = NSLAB * SLAB + (slab / 3) * 8;
    const uint32_t bars = sbase + OFF_BAR;
    TR_INIT

    const uint32_t x_bytes = has_extra ? CHUNK_BYTES : SLAB * 128;
    auto load_x = [&](int j) {
        asm volatile("mbarrier.arrive.expect_tx.shared::cta.b64 _, [%0], %1;" ::"r"(bars + j * 8), "r"(x_bytes) : "memory");
        tma_load(sbase + j * CHUNK_BYTES, &tm_x, bars + j * 8, j * 64, slab * SLAB);
        if (has_extra) tma_load(sbase + j * CHUNK_BYTES + SLAB * 128, &tm_xe, bars + j * 8, j * 64, s_extra);
    };
    if (warp == 8 && elect_one()) {
#pragma unroll
        for (int i = 0; i < NG; i++) mbar_init(bars + i * 8, 1);
        asm volatile("fence.mbarrier_init.release.cluster;" ::: "memory");
#pragma unroll
        for (int j = 0; j < NEARLY; j++) load_x(j);
    }
    if (warp >= 10 && elect_one()) {
        const int w = warp - 10;
        const uint32_t b = bars + NG * 8 + w * B_BLOCK;
#pragma unroll
        for (int i = 0; i < B_BLOCK; i += 8)
            mbar_init(b + i, (i == B_SFREE || i == B_WFULL || i == B_WFULL + 8) ? 1 : 4);
        asm volatile("fence.mbarrier_init.release.cluster;" ::: "memory");
    }

    if (warp >= 8) {
        const bool is_server = warp < 10;
        asm volatile("setmaxnreg.dec.sync.aligned.u32 %0;" ::"n"(504 - 2 * CREG));
        const int w = __shfl_sync(0xffffffffu, (threadIdx.x >> 5) & 1, 0);
        const uint32_t wb = bars + NG * 8 + w * B_BLOCK;
        asm volatile("bar.arrive 0, 384;" ::: "memory");
        if (is_server) {
            const bool leader = elect_one();
            if (leader && w == 0) {
                uint32_t t0 = clock();
#pragma unroll 1
                for (int j = NEARLY; j < NG; j++) {
                    while ((uint32_t)clock() - t0 < PACE) {}
                    t0 += PACE;
                    load_x(j);
                }
            }
            __syncwarp();
            asm volatile("bar.sync 2, 128;" ::: "memory");
            if (leader) {
                asm volatile("prefetch.tensormap [%0];" ::"l"(&tm_o) : "memory");
                asm volatile("prefetch.tensormap [%0];" ::"l"(&tm_oe) : "memory");
                const uint32_t stage = sbase + OFF_STAGE + w * PIECE_BYTES;
                int f0 = f_cta + rot * 128 + w * 64;
#pragma unroll 1
                for (int round = 0; round < ((ABL & 1) ? 0 : 2); round++) {
#pragma unroll
                    for (int p = 0; p < NPIECE; p++) {
                        mbar_wait(wb + B_SFULL, p & 1);
                        asm volatile("fence.proxy.async.shared::cta;" ::: "memory");
                        tma_store3(&tm_o, stage, f0, p * 16, slab);
                        if (p == NPIECE - 1 && round == 0 && has_extra)
                            asm volatile("cp.async.bulk.tensor.2d.global.shared::cta.bulk_group [%0, {%2, %3}], [%1];"
                                         ::"l"(&tm_oe), "r"(stage + 1024), "r"(f0), "r"(s_extra) : "memory");
                        asm volatile("cp.async.bulk.commit_group;" ::: "memory");
                        asm volatile("cp.async.bulk.wait_group.read 0;" ::: "memory");
                        mbar_arrive(wb + B_SFREE);
                    }
                    f0 += rot + round == 2 ? -256 : 128;
                }
                f0 = f_cta + (rot == 0 ? 2 : rot - 1) * 128 + w * 64;
#pragma unroll
                for (int p = 0; p < ((ABL & 2) ? 0 : NPIECE); p += 2) {
                    mbar_wait(wb + B_FIN + p * 4, 0);
                    asm volatile("fence.proxy.async.shared::cta;" ::: "memory");
                    tma_store3(&tm_o, sbase + w * CHUNK_BYTES + p * PIECE_BYTES, f0, p * 16, slab);
                    tma_store3(&tm_o, sbase + w * CHUNK_BYTES + (p + 1) * PIECE_BYTES, f0, p * 16 + 16, slab);
                }
                asm volatile("cp.async.bulk.commit_group;" ::: "memory");
                asm volatile("cp.async.bulk.wait_group.read 0;" ::: "memory");
            }
        } else {
            asm volatile("bar.arrive 2, 128;" ::: "memory");
            if (elect_one() && !(ABL & 4)) {
                const uint32_t ring = sbase + OFF_RING + w * 2 * SLOT_BYTES;
                int f0 = f_cta + rot * 128 + w * 64, j = 1, pair = rot;
#pragma unroll 1
                for (int m = 0; m < 3 * NG - 1; m += 2) {
#pragma unroll
                    for (int slot = 0; slot < 2; slot++) {
                        if (m > 0) mbar_wait(wb + B_WFREE + slot * 8, ((m >> 1) + 1) & 1);
                        asm volatile("mbarrier.arrive.expect_tx.shared::cta.b64 _, [%0], %1;" ::"r"(wb + B_WFULL + slot * 8), "r"(SLOT_BYTES) : "memory");
                        tma_load(ring + slot * SLOT_BYTES, &tm_q, wb + B_WFULL + slot * 8, f0, j * 4);
                        tma_load(ring + slot * SLOT_BYTES + 1024, &tm_s, wb + B_WFULL + slot * 8, f0, j);
                        tma_load(ring + slot * SLOT_BYTES + 1152, &tm_z, wb + B_WFULL + slot * 8, f0, j);
                        if (++j == NG) {
                            j = 0;
                            f0 += pair == 2 ? -256 : 128;
                            pair = pair == 2 ? 0 : pair + 1;
                        }
                    }
                    if (L2D && m + 3 < NG) {
#pragma unroll
                        for (int d = 3; d < 5; d++) {
                            asm volatile("cp.async.bulk.prefetch.tensor.2d.L2.global [%0, {%1, %2}];" ::"l"(&tm_q), "r"(f0), "r"((m + d) * 4) : "memory");
                            asm volatile("cp.async.bulk.prefetch.tensor.2d.L2.global [%0, {%1, %2}];" ::"l"(&tm_s), "r"(f0), "r"(m + d) : "memory");
                            asm volatile("cp.async.bulk.prefetch.tensor.2d.L2.global [%0, {%1, %2}];" ::"l"(&tm_z), "r"(f0), "r"(m + d) : "memory");
                        }
                    }
                }
            }
        }
    } else {
        TRL(0);
        const int lane = threadIdx.x & 31, wq = (threadIdx.x >> 5) & 3;
        const int wg = __shfl_sync(0xffffffffu, threadIdx.x >> 7, 0);
        const int g = lane >> 2, t = lane & 3, sh = 4 * t;
        Raw raw0;
        load_raw(qw, scales, zeros, f_cta + wg * 64 + wq * 16 + rot * 128 + 2 * g, 0, raw0);
        asm volatile("setmaxnreg.inc.sync.aligned.u32 %0;" ::"n"(CREG));

        const uint64_t desc0 = (uint64_t)((sbase & 0x3FFFF) >> 4) | (1ull << 16) | (64ull << 32) | (1ull << 62);
        const uint32_t wb = bars + NG * 8 + wg * B_BLOCK;
        const uint32_t chunk = wq * 2 + (g >> 2);
        const uint32_t st0 = sbase + OFF_STAGE + wg * PIECE_BYTES + (2 * t) * 128 + ((chunk ^ (2 * t)) << 4) + (g & 3) * 4;
        const uint32_t st1 = (st0 ^ 16) + 128;
        const uint32_t ring_q = sbase + OFF_RING + wg * 2 * SLOT_BYTES + wq * 64 + g * 8;
        const uint32_t ring_s = sbase + OFF_RING + wg * 2 * SLOT_BYTES + 1024 + wq * 32 + g * 4;
        uint32_t c22;
        asm volatile("mov.b32 %0, 0x22;" : "=r"(c22));
        float acc[96];
        uint32_t a[2][4][4];
        uint32_t pk[48];
        asm volatile("bar.sync 0, 384;" ::: "memory");
        dequant(raw0, sh, c22, a[0]);
        TRL(1);

        auto put_blocks = [&](uint32_t off, int b0, int nb, uint32_t bar) {
#pragma unroll
            for (int b = 0; b < nb; b++) {
                asm volatile("st.shared.u32 [%0], %1;" ::"r"(st0 + off + b * 1024), "r"(pk[2 * (b0 + b)]) : "memory");
                asm volatile("st.shared.u32 [%0], %1;" ::"r"(st1 + off + b * 1024), "r"(pk[2 * (b0 + b) + 1]) : "memory");
            }
            __syncwarp();
            mbar_arrive_if(bar, lane);
        };
        auto piece = [&](int round, int p) {
            if (p < NPIECE && !(ABL & 1)) {
                if (p > 0 || round > 1) mbar_wait(wb + B_SFREE, (p + 1) & 1);
                put_blocks(0, 2 * p, 2, wb + B_SFULL);
            }
        };
        auto step = [&](auto ntag, int round, int j) {
            constexpr int N = decltype(ntag)::value;
            const int m = round * NG + j, slot = m & 1;
            wg_fence();
#pragma unroll
            for (int kk = 0; kk < 4; kk++)
                Wgmma<N>::rs(acc, a[m & 1][kk], desc0 + (uint64_t)(j * (CHUNK_BYTES >> 4) + kk * 2), (j | kk) != 0);
            wg_commit();
            if (N == 192 && STAG && j == STAG - 1 && wg == 0) asm volatile("bar.arrive 1, 256;" ::: "memory");
            if (m + 1 < 3 * NG) {
                Raw raw;
                if (!(ABL & 4)) {
                    mbar_wait(wb + B_WFULL + slot * 8, (m >> 1) & 1);
                    lds_raw(ring_q + slot * SLOT_BYTES, ring_s + slot * SLOT_BYTES, raw);
                    __syncwarp();
                    if (m + 3 < 3 * NG) mbar_arrive_if(wb + B_WFREE + slot * 8, lane);
                }
                if (N == 184) piece(round, j < DBL ? 1 + 2 * j : 1 + DBL + j);
                wg_wait<1>();
                if (m == 2 * NG + 2) mbar_arrive_if(wb + B_XDONE, lane);
                if (!(ABL & 4)) dequant(raw, sh, c22, a[(m + 1) & 1]);
                else if (m == 0) { for (int kk = 0; kk < 4; kk++) for (int q = 0; q < 4; q++) a[1][kk][q] = a[0][kk][q] ^ 0x80008000u; }
            } else piece(round, 1 + DBL + j);
            if (N == 184 && j < DBL) piece(round, 2 + 2 * j);
        };
        auto finish = [&](int nblk) {
            wg_wait<0>();
#pragma unroll
            for (int b = 0; b < nblk; b++) {
                pk[2 * b] = pack_bf2(acc[b * 4], acc[b * 4 + 2]);
                pk[2 * b + 1] = pack_bf2(acc[b * 4 + 1], acc[b * 4 + 3]);
            }
        };

        if (STAG && wg == 1) asm volatile("bar.sync 1, 256;" ::: "memory");
#pragma unroll
        for (int j = 0; j < NG; j++) {
            mbar_wait(bars + j * 8, 0);
            if (j == 0) { TRL(4); TRG(50); } else TR(4 + j);
            step(Int<192>{}, 0, j);
        }
        finish(24);
        TR(4 + 9);
#pragma unroll
        for (int round = 1; round < 3; round++) {
            piece(round, 0);
#pragma unroll
            for (int j = 0; j < NG; j++) {
                TR(4 + round * 12 + j);
                step(Int<184>{}, round, j);
            }
            finish(23);
            TRL(4 + round * 12 + 9);
        }
        mbar_wait(bars + NG * 8 + (wg ^ 1) * B_BLOCK + B_XDONE, 0);
        const uint32_t fin = wg * (CHUNK_BYTES - PIECE_BYTES) - OFF_STAGE;
#pragma unroll
        for (int p = 0; p < NPIECE / 2; p++) put_blocks(fin + p * 2 * PIECE_BYTES, 4 * p, p < 5 ? 4 : 3, wb + B_FIN + p * 8);
        TRL(3); TRG(51);
    }
}

typedef CUresult (*EncodeFn)(CUtensorMap*, CUtensorMapDataType, cuuint32_t, void*, const cuuint64_t*, const cuuint64_t*,
                             const cuuint32_t*, const cuuint32_t*, CUtensorMapInterleave, CUtensorMapSwizzle,
                             CUtensorMapL2promotion, CUtensorMapFloatOOBfill);

void make_map(EncodeFn fn, CUtensorMap* m, CUtensorMapDataType dt, CUtensorMapSwizzle sw, void* ptr, int rank,
              const cuuint64_t* dims, const cuuint64_t* strides, const cuuint32_t* box) {
    const cuuint32_t estr[3] = {1, 1, 1};
    fn(m, dt, rank, ptr, dims, strides, box, estr, CU_TENSOR_MAP_INTERLEAVE_NONE, sw,
       CU_TENSOR_MAP_L2_PROMOTION_L2_128B, CU_TENSOR_MAP_FLOAT_OOB_FILL_NONE);
}

}

extern "C" void kernel_launch(void* const* d_in, const int* in_sizes, int n_in, void* d_out, int out_size) {
    static EncodeFn encode = nullptr;
    if (!encode) {
        void* fn = nullptr;
        cudaDriverEntryPointQueryResult qr;
        cudaGetDriverEntryPoint("cuTensorMapEncodeTiled", &fn, cudaEnableDefault, &qr);
        encode = (EncodeFn)fn;
        cudaFuncSetAttribute(gptq_gemm_kernel, cudaFuncAttributeMaxDynamicSharedMemorySize, SMEM_BYTES);
    }
    CUtensorMap tm_x, tm_xe, tm_o, tm_oe, tm_q, tm_s, tm_z;
    const cuuint64_t xd[2] = {K_DIM, S_DIM}, xs[1] = {K_DIM * 2};
    const cuuint64_t od[2] = {F_DIM, S_DIM}, os[1] = {F_DIM * 2};
    const cuuint64_t od3[3] = {F_DIM, SLAB, NSLAB}, os3[2] = {F_DIM * 2, (cuuint64_t)F_DIM * 2 * SLAB};
    const cuuint32_t bx[2] = {64, SLAB}, b8[2] = {64, 8}, bo[3] = {64, 16, 1};
    const cuuint64_t qd[2] = {F_DIM, K_DIM / 16}, qs[1] = {F_DIM * 4}, sd[2] = {F_DIM, NG};
    const cuuint32_t bq[2] = {64, 4}, bs[2] = {64, 1};
    const CUtensorMapDataType BF = CU_TENSOR_MAP_DATA_TYPE_BFLOAT16;
    const CUtensorMapSwizzle SW = CU_TENSOR_MAP_SWIZZLE_128B, NO = CU_TENSOR_MAP_SWIZZLE_NONE;
    make_map(encode, &tm_x, BF, SW, d_in[0], 2, xd, xs, bx);
    make_map(encode, &tm_xe, BF, SW, d_in[0], 2, xd, xs, b8);
    make_map(encode, &tm_o, BF, SW, d_out, 3, od3, os3, bo);
    make_map(encode, &tm_oe, BF, SW, d_out, 2, od, os, b8);
    make_map(encode, &tm_q, CU_TENSOR_MAP_DATA_TYPE_INT32, NO, d_in[1], 2, qd, qs, bq);
    make_map(encode, &tm_s, BF, NO, d_in[2], 2, sd, os, bs);
    make_map(encode, &tm_z, BF, NO, d_in[3], 2, sd, os, bs);
    gptq_gemm_kernel<<<dim3(NFR, NSLAB), 384, SMEM_BYTES>>>(tm_x, tm_xe, tm_o, tm_oe, tm_q, tm_s, tm_z, (const int*)d_in[1],
                                                           (const __nv_bfloat16*)d_in[2], (const __nv_bfloat16*)d_in[3]);
}
```

```cpp
#include <cuda_runtime.h>
#include <cuda_bf16.h>
#include <cuda.h>
#include <stdint.h>

namespace {

constexpr int S_DIM = 2048, K_DIM = 576, F_DIM = 4608;
constexpr int NG = K_DIM / 64;
constexpr int NSTEP = 3 * NG;
constexpr int SLAB = 184, NSLAB = 11;
constexpr int NFR = 12, F_CTA = F_DIM / NFR;
constexpr int CHUNK_BYTES = 192 * 128;
constexpr int PIECE_BYTES = 16 * 128;
constexpr int PBLK = 4;
constexpr int NPIECE = 24 / PBLK;
constexpr int NFIN = 6;
constexpr int SLOT_BYTES = 1280;
constexpr int OFF_STAGE = NG * CHUNK_BYTES;
constexpr int OFF_RING = OFF_STAGE + 2 * PIECE_BYTES;
constexpr int OFF_BAR = OFF_RING + 4 * SLOT_BYTES;
constexpr int B_SFULL = 0, B_SFREE = 8, B_XDONE = 16, B_WFULL = 24, B_WFREE = 40, B_FIN = 56, B_SPARE = 104, B_BLOCK = 112;
constexpr int SMEM_BYTES = OFF_BAR + NG * 8 + 2 * B_BLOCK;

constexpr int HOLD_AT = 4;
constexpr int RELEASE_AT = 7;
constexpr int X_WINDOW = 4;
constexpr int CONSUMER_REGS = 232, HELPER_REGS = 40;

__device__ __forceinline__ bool elect_one() {
    uint32_t p;
    asm volatile("{\n.reg .pred q;\nelect.sync _|q, 0xffffffff;\nselp.u32 %0, 1, 0, q;\n}" : "=r"(p));
    return p;
}
__device__ __forceinline__ void mbar_init(uint32_t bar, uint32_t cnt) {
    asm volatile("mbarrier.init.shared::cta.b64 [%0], %1;" ::"r"(bar), "r"(cnt) : "memory");
}
__device__ __forceinline__ void mbar_init_fence() { asm volatile("fence.mbarrier_init.release.cluster;" ::: "memory"); }
__device__ __forceinline__ void mbar_wait(uint32_t bar, uint32_t parity) {
    asm volatile(
        "{\n.reg .pred p;\n"
        "LAB_WAIT:\n"
        "mbarrier.try_wait.parity.shared::cta.b64 p, [%0], %1;\n"
        "@p bra LAB_DONE;\n"
        "bra LAB_WAIT;\n"
        "LAB_DONE:\n}\n" ::"r"(bar), "r"(parity) : "memory");
}
__device__ __forceinline__ bool mbar_test(uint32_t bar, uint32_t parity) {
    uint32_t r;
    asm volatile("{\n.reg .pred p;\nmbarrier.test_wait.parity.shared::cta.b64 p, [%1], %2;\nselp.u32 %0, 1, 0, p;\n}\n" : "=r"(r) : "r"(bar), "r"(parity) : "memory");
    return r;
}
__device__ __forceinline__ void mbar_arrive(uint32_t bar) {
    asm volatile("mbarrier.arrive.shared::cta.b64 _, [%0];" ::"r"(bar) : "memory");
}
__device__ __forceinline__ void mbar_arrive_if_zero(uint32_t bar, uint32_t v) {
    asm volatile("{\n.reg .pred p;\nsetp.eq.u32 p, %1, 0;\n@p mbarrier.arrive.shared::cta.b64 _, [%0];\n}\n" ::"r"(bar), "r"(v) : "memory");
}
__device__ __forceinline__ void mbar_expect_tx(uint32_t bar, uint32_t bytes) {
    asm volatile("mbarrier.arrive.expect_tx.shared::cta.b64 _, [%0], %1;" ::"r"(bar), "r"(bytes) : "memory");
}
__device__ __forceinline__ void tma_load(uint32_t dst, const CUtensorMap* tm, uint32_t bar, int c0, int c1) {
    asm volatile("cp.async.bulk.tensor.2d.shared::cluster.global.mbarrier::complete_tx::bytes [%0], [%1, {%3, %4}], [%2];"
                 ::"r"(dst), "l"(tm), "r"(bar), "r"(c0), "r"(c1) : "memory");
}
__device__ __forceinline__ void tma_store2(const CUtensorMap* tm, uint32_t src, int c0, int c1) {
    asm volatile("cp.async.bulk.tensor.2d.global.shared::cta.bulk_group [%0, {%2, %3}], [%1];"
                 ::"l"(tm), "r"(src), "r"(c0), "r"(c1) : "memory");
}
__device__ __forceinline__ void tma_store3(const CUtensorMap* tm, uint32_t src, int c0, int c1, int c2) {
    asm volatile("cp.async.bulk.tensor.3d.global.shared::cta.bulk_group [%0, {%2, %3, %4}], [%1];"
                 ::"l"(tm), "r"(src), "r"(c0), "r"(c1), "r"(c2) : "memory");
}
__device__ __forceinline__ void tma_store_drain() {
    asm volatile("cp.async.bulk.commit_group;" ::: "memory");
    asm volatile("cp.async.bulk.wait_group.read 0;" ::: "memory");
}
__device__ __forceinline__ void proxy_fence() { asm volatile("fence.proxy.async.shared::cta;" ::: "memory"); }

template <int N> struct Wgmma;
template <> struct Wgmma<192> {
    static __device__ __forceinline__ void rs(float (&d)[96], const uint32_t (&a)[4], uint32_t dbase, int doff, int scale_d) {
        asm volatile(
            "{\n.reg .pred p;\n.reg .b32 lo;\n.reg .b64 desc;\n"
            "setp.ne.b32 p, %101, 0;\nadd.u32 lo, %100, %102;\nmov.b64 desc, {lo, 0x40000040};\n"
            "wgmma.mma_async.sync.aligned.m64n192k16.f32.bf16.bf16 {"
            "%0,%1,%2,%3,%4,%5,%6,%7,%8,%9,%10,%11,%12,%13,%14,%15,%16,%17,%18,%19,%20,%21,%22,%23,"
            "%24,%25,%26,%27,%28,%29,%30,%31,%32,%33,%34,%35,%36,%37,%38,%39,%40,%41,%42,%43,%44,%45,%46,%47,"
            "%48,%49,%50,%51,%52,%53,%54,%55,%56,%57,%58,%59,%60,%61,%62,%63,%64,%65,%66,%67,%68,%69,%70,%71,"
            "%72,%73,%74,%75,%76,%77,%78,%79,%80,%81,%82,%83,%84,%85,%86,%87,%88,%89,%90,%91,%92,%93,%94,%95}, "
            "{%96,%97,%98,%99}, desc, p, 1, 1, 0;\n}\n"
            : "+f"(d[0]), "+f"(d[1]), "+f"(d[2]), "+f"(d[3]), "+f"(d[4]), "+f"(d[5]), "+f"(d[6]), "+f"(d[7]),
              "+f"(d[8]), "+f"(d[9]), "+f"(d[10]), "+f"(d[11]), "+f"(d[12]), "+f"(d[13]), "+f"(d[14]), "+f"(d[15]),
              "+f"(d[16]), "+f"(d[17]), "+f"(d[18]), "+f"(d[19]), "+f"(d[20]), "+f"(d[21]), "+f"(d[22]), "+f"(d[23]),
              "+f"(d[24]), "+f"(d[25]), "+f"(d[26]), "+f"(d[27]), "+f"(d[28]), "+f"(d[29]), "+f"(d[30]), "+f"(d[31]),
              "+f"(d[32]), "+f"(d[33]), "+f"(d[34]), "+f"(d[35]), "+f"(d[36]), "+f"(d[37]), "+f"(d[38]), "+f"(d[39]),
              "+f"(d[40]), "+f"(d[41]), "+f"(d[42]), "+f"(d[43]), "+f"(d[44]), "+f"(d[45]), "+f"(d[46]), "+f"(d[47]),
              "+f"(d[48]), "+f"(d[49]), "+f"(d[50]), "+f"(d[51]), "+f"(d[52]), "+f"(d[53]), "+f"(d[54]), "+f"(d[55]),
              "+f"(d[56]), "+f"(d[57]), "+f"(d[58]), "+f"(d[59]), "+f"(d[60]), "+f"(d[61]), "+f"(d[62]), "+f"(d[63]),
              "+f"(d[64]), "+f"(d[65]), "+f"(d[66]), "+f"(d[67]), "+f"(d[68]), "+f"(d[69]), "+f"(d[70]), "+f"(d[71]),
              "+f"(d[72]), "+f"(d[73]), "+f"(d[74]), "+f"(d[75]), "+f"(d[76]), "+f"(d[77]), "+f"(d[78]), "+f"(d[79]),
              "+f"(d[80]), "+f"(d[81]), "+f"(d[82]), "+f"(d[83]), "+f"(d[84]), "+f"(d[85]), "+f"(d[86]), "+f"(d[87]),
              "+f"(d[88]), "+f"(d[89]), "+f"(d[90]), "+f"(d[91]), "+f"(d[92]), "+f"(d[93]), "+f"(d[94]), "+f"(d[95])
            : "r"(a[0]), "r"(a[1]), "r"(a[2]), "r"(a[3]), "r"(dbase), "r"(scale_d), "r"(doff));
    }
};
template <> struct Wgmma<184> {
    static __device__ __forceinline__ void rs(float (&d)[96], const uint32_t (&a)[4], uint32_t dbase, int doff, int scale_d) {
        asm volatile(
            "{\n.reg .pred p;\n.reg .b32 lo;\n.reg .b64 desc;\n"
            "setp.ne.b32 p, %97, 0;\nadd.u32 lo, %96, %98;\nmov.b64 desc, {lo, 0x40000040};\n"
            "wgmma.mma_async.sync.aligned.m64n184k16.f32.bf16.bf16 {"
            "%0,%1,%2,%3,%4,%5,%6,%7,%8,%9,%10,%11,%12,%13,%14,%15,%16,%17,%18,%19,%20,%21,%22,%23,"
            "%24,%25,%26,%27,%28,%29,%30,%31,%32,%33,%34,%35,%36,%37,%38,%39,%40,%41,%42,%43,%44,%45,%46,%47,"
            "%48,%49,%50,%51,%52,%53,%54,%55,%56,%57,%58,%59,%60,%61,%62,%63,%64,%65,%66,%67,%68,%69,%70,%71,"
            "%72,%73,%74,%75,%76,%77,%78,%79,%80,%81,%82,%83,%84,%85,%86,%87,%88,%89,%90,%91}, "
            "{%92,%93,%94,%95}, desc, p, 1, 1, 0;\n}\n"
            : "+f"(d[0]), "+f"(d[1]), "+f"(d[2]), "+f"(d[3]), "+f"(d[4]), "+f"(d[5]), "+f"(d[6]), "+f"(d[7]),
              "+f"(d[8]), "+f"(d[9]), "+f"(d[10]), "+f"(d[11]), "+f"(d[12]), "+f"(d[13]), "+f"(d[14]), "+f"(d[15]),
              "+f"(d[16]), "+f"(d[17]), "+f"(d[18]), "+f"(d[19]), "+f"(d[20]), "+f"(d[21]), "+f"(d[22]), "+f"(d[23]),
              "+f"(d[24]), "+f"(d[25]), "+f"(d[26]), "+f"(d[27]), "+f"(d[28]), "+f"(d[29]), "+f"(d[30]), "+f"(d[31]),
              "+f"(d[32]), "+f"(d[33]), "+f"(d[34]), "+f"(d[35]), "+f"(d[36]), "+f"(d[37]), "+f"(d[38]), "+f"(d[39]),
              "+f"(d[40]), "+f"(d[41]), "+f"(d[42]), "+f"(d[43]), "+f"(d[44]), "+f"(d[45]), "+f"(d[46]), "+f"(d[47]),
              "+f"(d[48]), "+f"(d[49]), "+f"(d[50]), "+f"(d[51]), "+f"(d[52]), "+f"(d[53]), "+f"(d[54]), "+f"(d[55]),
              "+f"(d[56]), "+f"(d[57]), "+f"(d[58]), "+f"(d[59]), "+f"(d[60]), "+f"(d[61]), "+f"(d[62]), "+f"(d[63]),
              "+f"(d[64]), "+f"(d[65]), "+f"(d[66]), "+f"(d[67]), "+f"(d[68]), "+f"(d[69]), "+f"(d[70]), "+f"(d[71]),
              "+f"(d[72]), "+f"(d[73]), "+f"(d[74]), "+f"(d[75]), "+f"(d[76]), "+f"(d[77]), "+f"(d[78]), "+f"(d[79]),
              "+f"(d[80]), "+f"(d[81]), "+f"(d[82]), "+f"(d[83]), "+f"(d[84]), "+f"(d[85]), "+f"(d[86]), "+f"(d[87]),
              "+f"(d[88]), "+f"(d[89]), "+f"(d[90]), "+f"(d[91])
            : "r"(a[0]), "r"(a[1]), "r"(a[2]), "r"(a[3]), "r"(dbase), "r"(scale_d), "r"(doff));
    }
};

__device__ __forceinline__ void wg_fence() { asm volatile("wgmma.fence.sync.aligned;" ::: "memory"); }
__device__ __forceinline__ void wg_commit() { asm volatile("wgmma.commit_group.sync.aligned;" ::: "memory"); }
template <int N> __device__ __forceinline__ void wg_wait() { asm volatile("wgmma.wait_group.sync.aligned %0;" ::"n"(N) : "memory"); }

__device__ __forceinline__ uint32_t prmt(uint32_t a, uint32_t b, uint32_t c) {
    uint32_t d;
    asm("prmt.b32 %0, %1, %2, %3;" : "=r"(d) : "r"(a), "r"(b), "r"(c));
    return d;
}
__device__ __forceinline__ uint32_t pack_bf2(float lo, float hi) {
    uint32_t d;
    asm("cvt.rn.bf16x2.f32 %0, %1, %2;" : "=r"(d) : "f"(hi), "f"(lo));
    return d;
}
__device__ __forceinline__ uint32_t hi2lo(uint32_t x) {
    uint32_t d;
    asm("{.reg .b16 l, h; .reg .b32 t; mov.b32 {l, h}, %1; mov.b32 t, {h, h}; add.rn.f16x2 %0, t, %2;}"
        : "=r"(d) : "r"(x), "r"(0x80008000u));
    return d;
}
template <int H> __device__ __forceinline__ uint32_t lut2(uint32_t q2, uint32_t z2, uint32_t s2) {
    uint32_t d;
    if (H == 0)
        asm("{.reg .b16 l, h; .reg .b32 z, s, t; mov.b32 {l, h}, %2; mov.b32 z, {l, l}; mov.b32 {l, h}, %3; mov.b32 s, {l, l};"
            " sub.rn.bf16x2 t, %1, z; mul.rn.bf16x2 %0, t, s;}" : "=r"(d) : "r"(q2), "r"(z2), "r"(s2));
    else
        asm("{.reg .b16 l, h; .reg .b32 z, s, t; mov.b32 {l, h}, %2; mov.b32 z, {h, h}; mov.b32 {l, h}, %3; mov.b32 s, {h, h};"
            " sub.rn.bf16x2 t, %1, z; mul.rn.bf16x2 %0, t, s;}" : "=r"(d) : "r"(q2), "r"(z2), "r"(s2));
    return d;
}

struct Raw { uint32_t w[4][2], s2, z2; };
struct Zeros { uint32_t v[3]; };
template <int V> struct Int { static constexpr int value = V; };

__device__ __forceinline__ void dequant(const Raw& r, int sh, uint32_t c22, uint32_t (&a)[4][4]) {
    const uint32_t l[2][2] = {{lut2<0>(0x3F800000u, r.z2, r.s2), lut2<0>(0x40404000u, r.z2, r.s2)},
                              {lut2<1>(0x3F800000u, r.z2, r.s2), lut2<1>(0x40404000u, r.z2, r.s2)}};
#pragma unroll
    for (int kk = 0; kk < 4; kk++)
#pragma unroll
        for (int h = 0; h < 2; h++) {
            const uint32_t u = r.w[kk][h] >> sh;
            const uint32_t sel = ((u & 0x000C000Cu) * 0x40u + (u & 0x00030003u)) * c22 + 0x10101010u;
            a[kk][h] = prmt(l[h][0], l[h][1], sel);
            a[kk][h + 2] = prmt(l[h][0], l[h][1], hi2lo(sel));
        }
}

__global__ void __launch_bounds__(384, 1)
gptq_gemm_kernel(const int* __restrict__ qw, const __nv_bfloat16* __restrict__ scales,
                 const __nv_bfloat16* __restrict__ zeros, const Zeros zero,
                 const __grid_constant__ CUtensorMap tm_x, const __grid_constant__ CUtensorMap tm_xe,
                 const __grid_constant__ CUtensorMap tm_o, const __grid_constant__ CUtensorMap tm_oe,
                 const __grid_constant__ CUtensorMap tm_q, const __grid_constant__ CUtensorMap tm_s,
                 const __grid_constant__ CUtensorMap tm_z) {
    extern __shared__ __align__(1024) uint8_t smem[];
    const uint32_t sbase = (uint32_t)__cvta_generic_to_shared(smem);
    const int warp = __shfl_sync(0xffffffffu, threadIdx.x >> 5, 0);
    const uint32_t bars = sbase + OFF_BAR;

    if (warp == 8 && elect_one()) {
        mbar_init(bars, 2);
        mbar_init_fence();
        mbar_expect_tx(bars, SLAB * 128);
        tma_load(sbase, &tm_x, bars, 0, blockIdx.y * SLAB);
    }
    if (warp >= 8) asm volatile("setmaxnreg.dec.sync.aligned.u32 %0;" ::"n"(HELPER_REGS));
    int slab, fr;
    asm volatile("mov.u32 %0, %ctaid.y;" : "=r"(slab));
    asm volatile("mov.u32 %0, %ctaid.x;" : "=r"(fr));
    const int rot = slab % 3;
    const int f_first = fr * F_CTA + rot * 128;
    const bool has_extra = slab < 9;
    const int s_extra = NSLAB * SLAB + (slab / 3) * 8;
    const uint32_t x_bytes = has_extra ? CHUNK_BYTES : SLAB * 128;
    auto next_pair = [&](int tile) { return rot + tile == 2 ? -256 : 128; };
    auto load_w = [&](uint32_t dst, uint32_t bar, int f, int j) {
        mbar_expect_tx(bar, SLOT_BYTES);
        tma_load(dst, &tm_q, bar, f, j * 4);
        tma_load(dst + 1024, &tm_s, bar, f, j);
        tma_load(dst + 1152, &tm_z, bar, f, j);
    };
    if (warp == 8 && elect_one()) {
        mbar_expect_tx(bars, x_bytes - SLAB * 128);
        if (has_extra) tma_load(sbase + SLAB * 128, &tm_xe, bars, 0, s_extra);
#pragma unroll
        for (int i = 1; i < NG; i++) mbar_init(bars + i * 8, 1);
        mbar_init_fence();
    }
    if (warp >= 10 && elect_one()) {
        const int w = warp - 10;
        const uint32_t b = bars + NG * 8 + w * B_BLOCK;
        mbar_init(b + B_WFULL, 1);
        mbar_init(b + B_WFULL + 8, 1);
        mbar_init_fence();
#pragma unroll
        for (int slot = 0; slot < 2; slot++)
            load_w(sbase + OFF_RING + (w * 2 + slot) * SLOT_BYTES, b + B_WFULL + slot * 8, f_first + w * 64, 1 + slot);
#pragma unroll
        for (int i = 0; i < B_BLOCK; i += 8)
            if (i != B_WFULL && i != B_WFULL + 8) mbar_init(b + i, i == B_SFREE ? 1 : 4);
        mbar_init_fence();
    }

    if (warp >= 8) {
        const bool is_store_warp = warp < 10;
        const int w = __shfl_sync(0xffffffffu, (threadIdx.x >> 5) & 1, 0);
        const uint32_t wb = bars + NG * 8 + w * B_BLOCK;
        int f0 = f_first + w * 64;
        asm volatile("bar.arrive 0, 384;" ::: "memory");
        if (is_store_warp) {
            const bool leader = elect_one();
            if (leader && w == 0) {
#pragma unroll 1
                for (int j = 1; j < NG; j++) {
                    if (j >= 2) mbar_wait(bars + (j < X_WINDOW ? 0 : j - X_WINDOW) * 8, 0);
                    mbar_expect_tx(bars + j * 8, x_bytes);
                    tma_load(sbase + j * CHUNK_BYTES, &tm_x, bars + j * 8, j * 64, slab * SLAB);
                    if (has_extra) tma_load(sbase + j * CHUNK_BYTES + SLAB * 128, &tm_xe, bars + j * 8, j * 64, s_extra);
                }
            }
            __syncwarp();
            asm volatile("bar.sync 2, 128;" ::: "memory");
            if (leader) {
                asm volatile("prefetch.tensormap [%0];" ::"l"(&tm_o) : "memory");
                asm volatile("prefetch.tensormap [%0];" ::"l"(&tm_oe) : "memory");
                const uint32_t stage = sbase + OFF_STAGE + w * PIECE_BYTES, spare = sbase + w * (PBLK - 2) * CHUNK_BYTES + SLAB * 128;
#pragma unroll 1
                for (int tile = 0; tile < 2; tile++) {
#pragma unroll
                    for (int p = 0; p < NPIECE; p++) {
                        mbar_wait(wb + B_SFULL, p & 1);
                        proxy_fence();
                        tma_store3(&tm_o, stage, f0, p * PBLK * 8, slab);
#pragma unroll
                        for (int b = 2; b < PBLK; b++) {
                            if (p * PBLK + b < 23) tma_store2(&tm_oe, spare + (b - 2) * CHUNK_BYTES, f0, slab * SLAB + (p * PBLK + b) * 8);
                            else if (tile == 0 && has_extra) tma_store2(&tm_oe, spare + (b - 2) * CHUNK_BYTES, f0, s_extra);
                        }
                        tma_store_drain();
                        mbar_arrive(wb + B_SFREE);
                    }
                    f0 += next_pair(tile);
                }
#pragma unroll
                for (int p = 0; p < 2 * NFIN; p += 2) {
                    mbar_wait(wb + B_FIN + p * 4, 0);
                    proxy_fence();
                    tma_store3(&tm_o, sbase + w * CHUNK_BYTES + p * PIECE_BYTES, f0, p * 16, slab);
                    tma_store3(&tm_o, sbase + w * CHUNK_BYTES + (p + 1) * PIECE_BYTES, f0, p * 16 + 16, slab);
                }
                tma_store_drain();
            }
        } else {
            asm volatile("bar.arrive 2, 128;" ::: "memory");
            if (elect_one()) {
                const uint32_t ring = sbase + OFF_RING + w * 2 * SLOT_BYTES;
#pragma unroll
                for (int i = 2; i < NSTEP - 1; i++) {
                    const int n = i + 1, slot = i & 1;
                    if (n % NG == 0) f0 += next_pair(n / NG - 1);
                    mbar_wait(wb + B_WFREE + slot * 8, ((i >> 1) + 1) & 1);
                    proxy_fence();
                    load_w(ring + slot * SLOT_BYTES, wb + B_WFULL + slot * 8, f0, n % NG);
                }
            }
        }
    } else {
        const int lane = threadIdx.x & 31, wq = (threadIdx.x >> 5) & 3;
        const int wg = __shfl_sync(0xffffffffu, threadIdx.x >> 7, 0);
        const int g = lane >> 2, t = lane & 3, sh = 4 * t;
        Raw raw0;
        {
            const uint32_t f = f_first + wg * 64 + wq * 16 + 2 * g;
#pragma unroll
            for (int kk = 0; kk < 4; kk++)
                asm volatile("ld.global.nc.v2.u32 {%0,%1}, [%2];" : "=r"(raw0.w[kk][0]), "=r"(raw0.w[kk][1]) : "l"(qw + kk * F_DIM + f));
            asm volatile("ld.global.nc.u32 %0, [%1];" : "=r"(raw0.s2) : "l"(scales + f));
            asm volatile("ld.global.nc.u32 %0, [%1];" : "=r"(raw0.z2) : "l"(zeros + f));
        }
        asm volatile("setmaxnreg.inc.sync.aligned.u32 %0;" ::"n"(CONSUMER_REGS));

        const uint32_t desc0 = ((sbase & 0x3FFFF) >> 4) | (1u << 16);
        const uint32_t wb = bars + NG * 8 + wg * B_BLOCK;
        const uint32_t st0 = sbase + OFF_STAGE + wg * PIECE_BYTES + (2 * t) * 128 + (((wq * 2 + (g >> 2)) ^ (2 * t)) << 4) + (g & 3) * 4;
        const uint32_t st1 = (st0 ^ 16) + 128;
        const uint32_t ring_q = sbase + OFF_RING + wg * 2 * SLOT_BYTES + wq * 64 + g * 8;
        const uint32_t ring_s = sbase + OFF_RING + wg * 2 * SLOT_BYTES + 1024 + wq * 32 + g * 4;
        uint32_t c22;
        asm volatile("mov.b32 %0, 0x22;" : "=r"(c22));
        float acc[96];
        uint32_t a[2][4][4];
        uint32_t pk[48];
        asm volatile("bar.sync 0, 384;" ::: "memory");
        dequant(raw0, sh, c22, a[0]);

        auto pack = [&](int b0, int b1) {
#pragma unroll
            for (int b = b0; b < b1; b++) {
                pk[2 * b] = pack_bf2(acc[b * 4], acc[b * 4 + 2]);
                pk[2 * b + 1] = pack_bf2(acc[b * 4 + 1], acc[b * 4 + 3]);
            }
        };
        auto put_block = [&](uint32_t off, int b) {
            asm volatile("st.shared.u32 [%0], %1;" ::"r"(st0 + off), "r"(pk[2 * b]) : "memory");
            asm volatile("st.shared.u32 [%0], %1;" ::"r"(st1 + off), "r"(pk[2 * b + 1]) : "memory");
        };
        auto publish = [&](uint32_t bar) {
            __syncwarp();
            mbar_arrive_if_zero(bar, lane);
        };
        const uint32_t own_chunk = wg * (CHUNK_BYTES - PIECE_BYTES) - OFF_STAGE;
        const uint32_t spare = wg * ((PBLK - 2) * CHUNK_BYTES - PIECE_BYTES) - OFF_STAGE + SLAB * 128;
        auto piece = [&](int tile, int p) {
            if (p > 0) mbar_wait(wb + B_SFREE, (p + 1) & 1);
            put_block(0, PBLK * p);
            put_block(1024, PBLK * p + 1);
#pragma unroll
            for (int b = 2; b < PBLK; b++)
                if (PBLK * p + b < 23 || tile == 1) put_block(spare + (b - 2) * CHUNK_BYTES, PBLK * p + b);
            publish(wb + B_SFULL);
        };
        auto step = [&](auto ntag, int tile, int j) {
            constexpr int N = decltype(ntag)::value;
            const int m = tile * NG + j, slot = m & 1;
            const int p = j + 1;
            const bool ready = m + 1 < NSTEP && mbar_test(wb + B_WFULL + slot * 8, (m >> 1) & 1);
            wg_fence();
#pragma unroll
            for (int kk = 0; kk < 4; kk++)
                Wgmma<N>::rs(acc, a[m & 1][kk], desc0 + zero.v[tile], j * (CHUNK_BYTES >> 4) + kk * 2, (j | kk) != 0);
            wg_commit();
            if (m == RELEASE_AT && wg == 0) asm volatile("bar.arrive 1, 256;" ::: "memory");
            if (m + 1 < NSTEP) {
                Raw raw;
                if (!ready) mbar_wait(wb + B_WFULL + slot * 8, (m >> 1) & 1);
#pragma unroll
                for (int kk = 0; kk < 4; kk++)
                    asm volatile("ld.shared.v2.u32 {%0,%1}, [%2];" : "=r"(raw.w[kk][0]), "=r"(raw.w[kk][1])
                                 : "r"(ring_q + slot * SLOT_BYTES + kk * 256) : "memory");
                asm volatile("ld.shared.u32 %0, [%1];" : "=r"(raw.s2) : "r"(ring_s + slot * SLOT_BYTES) : "memory");
                asm volatile("ld.shared.u32 %0, [%1];" : "=r"(raw.z2) : "r"(ring_s + slot * SLOT_BYTES + 128) : "memory");
                __syncwarp();
                if (m + 3 < NSTEP) mbar_arrive_if_zero(wb + B_WFREE + slot * 8, lane);
                if (tile > 0 && p < NPIECE) piece(tile, p);
                else mbar_wait(bars + (m + 1 < NG ? m + 1 : 0) * 8, 0);
                wg_wait<1>();
                if (m == PBLK - 2) mbar_arrive_if_zero(wb + B_SPARE, lane | (wg ^ 1));
                if (m == 2 * (PBLK - 2)) mbar_arrive_if_zero(wb + B_SPARE, lane | wg);
                if (m == 2 * NG + 1) mbar_arrive_if_zero(wb + B_XDONE, lane | (wg ^ 1));
                if (m == 2 * NG + 2) mbar_arrive_if_zero(wb + B_XDONE, lane | wg);
                dequant(raw, sh, c22, a[(m + 1) & 1]);
            }
        };

        mbar_wait(bars, 0);
#pragma unroll
        for (int j = 0; j < NG; j++) {
            if (j == HOLD_AT && wg == 1) asm volatile("bar.sync 1, 256;" ::: "memory");
            step(Int<192>{}, 0, j);
        }
#pragma unroll
        for (int tile = 1; tile < 3; tile++) {
            if (tile == 1) mbar_wait(bars + NG * 8 + (wg ^ 1) * B_BLOCK + B_SPARE, 0);
            else mbar_wait(wb + B_SFREE, 1);
            wg_wait<0>();
            pack(0, tile == 1 ? 24 : 23);
            piece(tile, 0);
#pragma unroll
            for (int j = 0; j < NG; j++) step(Int<184>{}, tile, j);
        }
        mbar_wait(bars + NG * 8 + (wg ^ 1) * B_BLOCK + B_XDONE, 0);
        wg_wait<0>();
#pragma unroll
        for (int p = 0; p < NFIN; p++) {
            const int b1 = p < NFIN - 1 ? 4 * p + 4 : 23;
            pack(4 * p, b1);
#pragma unroll
            for (int b = 4 * p; b < b1; b++) put_block(own_chunk + b * 1024, b);
            publish(wb + B_FIN + p * 8);
        }
    }
}

typedef CUresult (*EncodeFn)(CUtensorMap*, CUtensorMapDataType, cuuint32_t, void*, const cuuint64_t*, const cuuint64_t*,
                             const cuuint32_t*, const cuuint32_t*, CUtensorMapInterleave, CUtensorMapSwizzle,
                             CUtensorMapL2promotion, CUtensorMapFloatOOBfill);

void make_map(EncodeFn fn, CUtensorMap* m, CUtensorMapDataType dt, CUtensorMapSwizzle sw, void* ptr, int rank,
              const cuuint64_t* dims, const cuuint64_t* strides, const cuuint32_t* box) {
    const cuuint32_t estr[3] = {1, 1, 1};
    fn(m, dt, rank, ptr, dims, strides, box, estr, CU_TENSOR_MAP_INTERLEAVE_NONE, sw,
       CU_TENSOR_MAP_L2_PROMOTION_L2_128B, CU_TENSOR_MAP_FLOAT_OOB_FILL_NONE);
}

}

extern "C" void kernel_launch(void* const* d_in, const int* in_sizes, int n_in, void* d_out, int out_size) {
    static EncodeFn encode = nullptr;
    if (!encode) {
        void* fn = nullptr;
        cudaDriverEntryPointQueryResult qr;
        cudaGetDriverEntryPoint("cuTensorMapEncodeTiled", &fn, cudaEnableDefault, &qr);
        encode = (EncodeFn)fn;
        cudaFuncSetAttribute(gptq_gemm_kernel, cudaFuncAttributeMaxDynamicSharedMemorySize, SMEM_BYTES);
    }
    const cuuint64_t xd[2] = {K_DIM, S_DIM}, xs[1] = {K_DIM * 2};
    const cuuint64_t od[2] = {F_DIM, S_DIM}, os[1] = {F_DIM * 2};
    const cuuint64_t od3[3] = {F_DIM, SLAB, NSLAB}, os3[2] = {F_DIM * 2, (cuuint64_t)F_DIM * 2 * SLAB};
    const cuuint64_t qd[2] = {F_DIM, K_DIM / 16}, qs[1] = {F_DIM * 4}, sd[2] = {F_DIM, NG};
    const cuuint32_t bx[2] = {64, SLAB}, b8[2] = {64, 8}, bo[3] = {64, 16, 1}, bq[2] = {64, 4}, bs[2] = {64, 1};
    const CUtensorMapDataType BF = CU_TENSOR_MAP_DATA_TYPE_BFLOAT16;
    const CUtensorMapSwizzle SW = CU_TENSOR_MAP_SWIZZLE_128B, NO = CU_TENSOR_MAP_SWIZZLE_NONE;
    CUtensorMap tm_x, tm_xe, tm_o, tm_oe, tm_q, tm_s, tm_z;
    make_map(encode, &tm_x, BF, SW, d_in[0], 2, xd, xs, bx);
    make_map(encode, &tm_xe, BF, SW, d_in[0], 2, xd, xs, b8);
    make_map(encode, &tm_o, BF, SW, d_out, 3, od3, os3, bo);
    make_map(encode, &tm_oe, BF, SW, d_out, 2, od, os, b8);
    make_map(encode, &tm_q, CU_TENSOR_MAP_DATA_TYPE_INT32, NO, d_in[1], 2, qd, qs, bq);
    make_map(encode, &tm_s, BF, NO, d_in[2], 2, sd, os, bs);
    make_map(encode, &tm_z, BF, NO, d_in[3], 2, sd, os, bs);
    gptq_gemm_kernel<<<dim3(NFR, NSLAB), 384, SMEM_BYTES>>>((const int*)d_in[1], (const __nv_bfloat16*)d_in[2],
                                                           (const __nv_bfloat16*)d_in[3], Zeros{}, tm_x, tm_xe, tm_o,
                                                           tm_oe, tm_q, tm_s, tm_z);
}
```
